```python
import torch

def _softmax(x, axis=-1):
    return torch.softmax(x, dim=axis)

def _gelu(x):
    return torch.nn.functional.gelu(x, approximate='tanh')

def _silu(x):
    return torch.nn.functional.silu(x)

def _sigmoid(x):
    return torch.sigmoid(x)

def _layernorm(x, axis=-1, eps=1e-05):
    m = x.mean(dim=axis, keepdim=True)
    v = x.var(dim=axis, keepdim=True, unbiased=False)
    return (x - m) / torch.sqrt(v + eps)

def _scatter_add(tgt, idx, src, axis=0):
    return tgt.clone().index_add_(axis, idx, src)

def _segment_sum(src, seg, n):
    out = torch.zeros((n,) + src.shape[1:], dtype=src.dtype)
    return out.index_add_(0, seg, src)

def _pad(x, pw):
    flat = tuple((v for pair in reversed(pw) for v in pair))
    return torch.nn.functional.pad(x, flat)
kernel_name = 'parallel_sum__memory_aug_recurrent_mem_tr__mixer_token_mlp__prompt'

def setup_inputs():

    _w = lambda a: (lambda t: t.to(torch.bfloat16) if t.is_floating_point() else t)(torch.as_tensor(a))

    def _A_setup():
        B, S, Dm = (1, 2048, 576)
        H, Dh = (32, 128)
        M, seg = (8, 32)
        seg = min(seg, S)
        S = S // seg * seg
        return {'x': _w((lambda *s: torch.randn(*s, dtype=torch.bfloat16) * 0.05)(B, S, Dm)), 'mem0': _w((lambda *s: torch.randn(*s, dtype=torch.bfloat16) * 0.2)(B, M, Dm)), 'Wq': _w((lambda *s: torch.randn(*s, dtype=torch.bfloat16) * 1.6)(Dm, H, Dh) * Dm ** (-0.5)), 'Wk': _w((lambda *s: torch.randn(*s, dtype=torch.bfloat16) * 1.6)(Dm, H, Dh) * Dm ** (-0.5)), 'Wv': _w((lambda *s: torch.randn(*s, dtype=torch.bfloat16) * 0.2)(Dm, H, Dh) * Dm ** (-0.5)), 'Wo': _w((lambda *s: torch.randn(*s, dtype=torch.bfloat16) * 0.2)(H, Dh, Dm) * (H * Dh) ** (-0.5)), 'seg_len': seg}
    _A_in = _A_setup()

    def _B_setup():
        B, S, D, F = (1, 2048, 576, 4608)
        return {'x': _w((lambda *s: torch.randn(*s, dtype=torch.bfloat16) * 0.05)(B, S, D)), 'w1': _w((lambda *s: torch.randn(*s, dtype=torch.bfloat16) * 0.4)(S, F) * S ** (-0.5)), 'b1': _w((lambda *s: torch.randn(*s, dtype=torch.bfloat16) * 3.2)(F) * 0.02), 'w2': _w((lambda *s: torch.randn(*s, dtype=torch.bfloat16) * 0.2)(F, S) * F ** (-0.5)), 'b2': _w((lambda *s: torch.randn(*s, dtype=torch.bfloat16) * 0.4)(S) * 0.02)}
    _B_in = _B_setup()
    return {'A_x': _A_in['x'], 'A_mem0': _A_in['mem0'], 'A_Wq': _A_in['Wq'], 'A_Wk': _A_in['Wk'], 'A_Wv': _A_in['Wv'], 'A_Wo': _A_in['Wo'], 'A_seg_len': _A_in['seg_len'], 'B_x': _B_in['x'], 'B_w1': _B_in['w1'], 'B_b1': _B_in['b1'], 'B_w2': _B_in['w2'], 'B_b2': _B_in['b2']}

def reference(A_x, A_mem0, A_Wq, A_Wk, A_Wv, A_Wo, A_seg_len, B_x, B_w1, B_b1, B_w2, B_b2):

    def _A_ref(x, mem0, Wq, Wk, Wv, Wo, seg_len):
        B, S, Dm = x.shape
        H, Dh = (Wq.shape[1], Wq.shape[2])
        M = mem0.shape[1]
        scale = Dh ** (-0.5)
        n_seg = S // seg_len
        L = M + seg_len
        idx = torch.arange(L)
        mask = (idx[:, None] < M) | (idx[:, None] >= idx[None, :])
        mem = mem0
        outs = []
        for s in range(n_seg):
            xs = x[:, s * seg_len:(s + 1) * seg_len, :].clone()
            h = torch.concatenate([mem, xs], axis=1)
            q = torch.einsum('btd,dhe->bhte', h, Wq)
            k = torch.einsum('btd,dhe->bhte', h, Wk)
            v = torch.einsum('btd,dhe->bhte', h, Wv)
            scores = torch.einsum('bhqe,bhke->bhqk', q, k) * scale
            scores = torch.where(mask[None, None], scores, -1000000000.0)
            p = _softmax(scores, axis=-1)
            o = torch.einsum('bhqk,bhke->bhqe', p, v)
            o = torch.einsum('bhte,hed->btd', o, Wo)
            mem = o[:, :M, :].clone()
            outs.append(o[:, M:, :])
        return torch.concatenate(outs, axis=1)

    def _B_ref(x, w1, b1, w2, b2):
        B, S, D = x.shape
        h = _layernorm(x, axis=-1)
        u = torch.einsum('bsd,sf->bdf', h, w1) + b1
        u = _gelu(u)
        y = torch.einsum('bdf,fs->bds', u, w2) + b2
        return (lambda x, *d: x.permute(*d))(y, 0, 2, 1)
    x = A_x
    xn = _layernorm(x, axis=-1)
    return x + _A_ref(xn, A_mem0, A_Wq, A_Wk, A_Wv, A_Wo, A_seg_len) + _B_ref(xn, B_w1, B_b1, B_w2, B_b2)
```

```cpp
#include <cuda_runtime.h>
#include <cuda_bf16.h>
#include <cuda.h>
#include <stdint.h>
typedef __nv_bfloat16 bf16;
constexpr int S_ = 2048, D_ = 576, HD = 4096, F_ = 4608;
constexpr int NCHAIN = 64, NSEG = 64;
constexpr int NST = 4, STAGE = 49152, STG_OFF = NST * STAGE, BAR_OFF = STG_OFF + 32768, SMEM_BYTES = BAR_OFF + 1024;
constexpr int N_IND = 512 + 108 + 96;
constexpr uint32_t SENT = 0xFFFFFFFFu;
constexpr int SPIN_LIMIT = 1 << 27;

__device__ bf16 g_xn[S_ * D_], g_hb[S_ * D_], g_K[S_ * HD], g_V[S_ * HD], g_O[S_ * HD], g_uT[F_ * D_];
__device__ bf16 g_mK[NSEG * 8 * HD], g_mV[NSEG * 8 * HD];
__device__ float g_acc[S_ * D_];
__device__ float4 g_red[4 * 1664];
__device__ uint32_t g_mem[8 * 2304];
constexpr int C_DEP = 0, C_IND = 32, C_QAT = 40, C_G1 = 64, C_CH4 = 72, C_FIN = 96, C_QA = 256, C_KV = 512, C_PROG = 1024, C_TOT = C_PROG + 64 * 32;
__device__ int g_cnt[C_TOT];

#define STAMP(c, i)
#define STAMPV(c, i, v)
#define STAMPC(c, i)
enum { M_XN, M_WQ, M_WK, M_WV, M_WO, M_W1, M_HB, M_W2, M_UT, M_K128, M_K32, M_K64, M_V128, M_V32, M_V64, M_O128, M_O64, M_MK, M_MV, M_NUM };
struct Params { CUtensorMap m[M_NUM]; const bf16* x; const bf16* b1; const bf16* b2; bf16* out; };

#define TRAP_IF(n, lim) asm volatile("{\n.reg .pred q;\nsetp.gt.s32 q, %0, %1;\n@q st.global.u32 [%2], %0;\n}" ::"r"(n), "n"(lim), "l"(0ull))
__device__ __forceinline__ uint32_t smem_u32(const void* p) { return (uint32_t)__cvta_generic_to_shared(p); }
__device__ __forceinline__ void mbar_init(uint32_t b, int c) { asm volatile("mbarrier.init.shared::cta.b64 [%0], %1;" ::"r"(b), "r"(c)); }
__device__ __forceinline__ void mbar_arrive(uint32_t b) { asm volatile("mbarrier.arrive.shared::cta.b64 _, [%0];" ::"r"(b) : "memory"); }
__device__ __forceinline__ void mbar_expect(uint32_t b, int n) { asm volatile("mbarrier.arrive.expect_tx.shared::cta.b64 _, [%0], %1;" ::"r"(b), "r"(n) : "memory"); }
__device__ __forceinline__ void mbar_wait(uint32_t b, int par) {
  uint32_t ok; int n = 0;
  do {
    asm volatile("{\n.reg .pred p;\nmbarrier.try_wait.parity.shared::cta.b64 p, [%1], %2;\nselp.u32 %0, 1, 0, p;\n}" : "=r"(ok) : "r"(b), "r"(par) : "memory");
    TRAP_IF(++n, SPIN_LIMIT);
  } while (!ok);
}
__device__ __forceinline__ void mbar_wait_cl(uint32_t b, int par) {
  uint32_t ok; int n = 0;
  do {
    asm volatile("{\n.reg .pred p;\nmbarrier.try_wait.parity.acquire.cluster.shared::cta.b64 p, [%1], %2;\nselp.u32 %0, 1, 0, p;\n}" : "=r"(ok) : "r"(b), "r"(par) : "memory");
    TRAP_IF(++n, SPIN_LIMIT);
  } while (!ok);
}
__device__ __forceinline__ void tma_ld(uint32_t dst, const CUtensorMap* m, int x, int y, uint32_t bar) {
  asm volatile("cp.async.bulk.tensor.2d.shared::cluster.global.mbarrier::complete_tx::bytes [%0], [%1, {%3, %4}], [%2];"
               ::"r"(dst), "l"(m), "r"(bar), "r"(x), "r"(y) : "memory");
}
__device__ __forceinline__ void tma_st(const CUtensorMap* m, uint32_t src, int x, int y) {
  asm volatile("cp.async.bulk.tensor.2d.global.shared::cta.bulk_group [%0, {%2, %3}], [%1];" ::"l"(m), "r"(src), "r"(x), "r"(y) : "memory");
}
__device__ __forceinline__ void griddep_wait() { asm volatile("griddepcontrol.wait;" ::: "memory"); }
__device__ __forceinline__ void fence_async() { asm volatile("fence.proxy.async;" ::: "memory"); }
__device__ __forceinline__ void fence_async_s() { asm volatile("fence.proxy.async.shared::cta;" ::: "memory"); }
__device__ __forceinline__ void bar_sync(int id, int n) { asm volatile("bar.sync %0, %1;" ::"r"(id), "r"(n) : "memory"); }
__device__ __forceinline__ int ld_acq(const int* p) { int v; asm volatile("ld.acquire.gpu.global.s32 %0, [%1];" : "=r"(v) : "l"(p) : "memory"); return v; }
__device__ __forceinline__ void red_rel(int* p, int v) { asm volatile("red.release.gpu.global.add.s32 [%0], %1;" ::"l"(p), "r"(v) : "memory"); }
__device__ __forceinline__ void spin_ge(const int* p, int v) { int n = 0; while (ld_acq(p) < v) { TRAP_IF(++n, SPIN_LIMIT >> 4); } }
__device__ __forceinline__ void wg_fence() { asm volatile("wgmma.fence.sync.aligned;" ::: "memory"); }
__device__ __forceinline__ void wg_commit() { asm volatile("wgmma.commit_group.sync.aligned;" ::: "memory"); }
template <int N> __device__ __forceinline__ void wg_wait() { asm volatile("wgmma.wait_group.sync.aligned %0;" ::"n"(N) : "memory"); }
__device__ __forceinline__ uint64_t mkdesc(uint32_t a, uint32_t lbo, uint32_t sbo, int sw) {
  return (uint64_t)((a & 0x3FFFF) >> 4) | ((uint64_t)(lbo >> 4) << 16) | ((uint64_t)(sbo >> 4) << 32) | ((uint64_t)sw << 62);
}
__device__ __forceinline__ uint32_t pack2(float a, float b) { __nv_bfloat162 v = __floats2bfloat162_rn(a, b); return *reinterpret_cast<uint32_t*>(&v); }
__device__ __forceinline__ void stsm4(uint32_t a, uint32_t r0, uint32_t r1, uint32_t r2, uint32_t r3) {
  asm volatile("stmatrix.sync.aligned.m8n8.x4.shared.b16 [%0], {%1,%2,%3,%4};" ::"r"(a), "r"(r0), "r"(r1), "r"(r2), "r"(r3) : "memory");
}
__device__ __forceinline__ void stsm2t(uint32_t a, uint32_t r0, uint32_t r1) {
  asm volatile("stmatrix.sync.aligned.m8n8.x2.trans.shared.b16 [%0], {%1,%2};" ::"r"(a), "r"(r0), "r"(r1) : "memory");
}
__device__ __forceinline__ void ldsm4(uint32_t a, uint32_t& r0, uint32_t& r1, uint32_t& r2, uint32_t& r3) {
  asm volatile("ldmatrix.sync.aligned.m8n8.x4.shared.b16 {%0,%1,%2,%3}, [%4];" : "=r"(r0), "=r"(r1), "=r"(r2), "=r"(r3) : "r"(a) : "memory");
}
__device__ __forceinline__ void ldsm4t(uint32_t a, uint32_t& r0, uint32_t& r1, uint32_t& r2, uint32_t& r3) {
  asm volatile("ldmatrix.sync.aligned.m8n8.x4.trans.shared.b16 {%0,%1,%2,%3}, [%4];" : "=r"(r0), "=r"(r1), "=r"(r2), "=r"(r3) : "r"(a) : "memory");
}
__device__ __forceinline__ void mma16816(float (&c)[4], uint32_t a0, uint32_t a1, uint32_t a2, uint32_t a3, uint32_t b0, uint32_t b1) {
  asm volatile("mma.sync.aligned.m16n8k16.row.col.f32.bf16.bf16.f32 {%0,%1,%2,%3}, {%4,%5,%6,%7}, {%8,%9}, {%0,%1,%2,%3};"
               : "+f"(c[0]), "+f"(c[1]), "+f"(c[2]), "+f"(c[3]) : "r"(a0), "r"(a1), "r"(a2), "r"(a3), "r"(b0), "r"(b1));
}
template <int N> __device__ __forceinline__ void keep(float (&d)[N]) {
#pragma unroll
  for (int i = 0; i < N; i++) asm volatile("" : "+f"(d[i])::"memory");
}
template <int N> __device__ __forceinline__ void zero(float (&d)[N]) {
#pragma unroll
  for (int i = 0; i < N; i++) d[i] = 0.f;
}
__device__ __forceinline__ void wg_ss_256_01(float (&d)[128], uint64_t da, uint64_t db, int sc) {
  asm volatile("{\n.reg .pred p;\nsetp.ne.b32 p, %130, 0;\n"
    "wgmma.mma_async.sync.aligned.m64n256k16.f32.bf16.bf16 {%0, %1, %2, %3, %4, %5, %6, %7, %8, %9, %10, %11, %12, %13, %14, %15, %16, %17, %18, %19, %20, %21, %22, %23, %24, %25, %26, %27, %28, %29, %30, %31, %32, %33, %34, %35, %36, %37, %38, %39, %40, %41, %42, %43, %44, %45, %46, %47, %48, %49, %50, %51, %52, %53, %54, %55, %56, %57, %58, %59, %60, %61, %62, %63, %64, %65, %66, %67, %68, %69, %70, %71, %72, %73, %74, %75, %76, %77, %78, %79, %80, %81, %82, %83, %84, %85, %86, %87, %88, %89, %90, %91, %92, %93, %94, %95, %96, %97, %98, %99, %100, %101, %102, %103, %104, %105, %106, %107, %108, %109, %110, %111, %112, %113, %114, %115, %116, %117, %118, %119, %120, %121, %122, %123, %124, %125, %126, %127}, %128, %129, p, 1, 1, 0, 1;\n}\n"
    : "+f"(d[0]), "+f"(d[1]), "+f"(d[2]), "+f"(d[3]), "+f"(d[4]), "+f"(d[5]), "+f"(d[6]), "+f"(d[7]), "+f"(d[8]), "+f"(d[9]), "+f"(d[10]), "+f"(d[11]), "+f"(d[12]), "+f"(d[13]), "+f"(d[14]), "+f"(d[15]), "+f"(d[16]), "+f"(d[17]), "+f"(d[18]), "+f"(d[19]), "+f"(d[20]), "+f"(d[21]), "+f"(d[22]), "+f"(d[23]), "+f"(d[24]), "+f"(d[25]), "+f"(d[26]), "+f"(d[27]), "+f"(d[28]), "+f"(d[29]), "+f"(d[30]), "+f"(d[31]), "+f"(d[32]), "+f"(d[33]), "+f"(d[34]), "+f"(d[35]), "+f"(d[36]), "+f"(d[37]), "+f"(d[38]), "+f"(d[39]), "+f"(d[40]), "+f"(d[41]), "+f"(d[42]), "+f"(d[43]), "+f"(d[44]), "+f"(d[45]), "+f"(d[46]), "+f"(d[47]), "+f"(d[48]), "+f"(d[49]), "+f"(d[50]), "+f"(d[51]), "+f"(d[52]), "+f"(d[53]), "+f"(d[54]), "+f"(d[55]), "+f"(d[56]), "+f"(d[57]), "+f"(d[58]), "+f"(d[59]), "+f"(d[60]), "+f"(d[61]), "+f"(d[62]), "+f"(d[63]), "+f"(d[64]), "+f"(d[65]), "+f"(d[66]), "+f"(d[67]), "+f"(d[68]), "+f"(d[69]), "+f"(d[70]), "+f"(d[71]), "+f"(d[72]), "+f"(d[73]), "+f"(d[74]), "+f"(d[75]), "+f"(d[76]), "+f"(d[77]), "+f"(d[78]), "+f"(d[79]), "+f"(d[80]), "+f"(d[81]), "+f"(d[82]), "+f"(d[83]), "+f"(d[84]), "+f"(d[85]), "+f"(d[86]), "+f"(d[87]), "+f"(d[88]), "+f"(d[89]), "+f"(d[90]), "+f"(d[91]), "+f"(d[92]), "+f"(d[93]), "+f"(d[94]), "+f"(d[95]), "+f"(d[96]), "+f"(d[97]), "+f"(d[98]), "+f"(d[99]), "+f"(d[100]), "+f"(d[101]), "+f"(d[102]), "+f"(d[103]), "+f"(d[104]), "+f"(d[105]), "+f"(d[106]), "+f"(d[107]), "+f"(d[108]), "+f"(d[109]), "+f"(d[110]), "+f"(d[111]), "+f"(d[112]), "+f"(d[113]), "+f"(d[114]), "+f"(d[115]), "+f"(d[116]), "+f"(d[117]), "+f"(d[118]), "+f"(d[119]), "+f"(d[120]), "+f"(d[121]), "+f"(d[122]), "+f"(d[123]), "+f"(d[124]), "+f"(d[125]), "+f"(d[126]), "+f"(d[127]) : "l"(da), "l"(db), "r"(sc));
}
__device__ __forceinline__ void wg_ss_192_01(float (&d)[96], uint64_t da, uint64_t db, int sc) {
  asm volatile("{\n.reg .pred p;\nsetp.ne.b32 p, %98, 0;\n"
    "wgmma.mma_async.sync.aligned.m64n192k16.f32.bf16.bf16 {%0, %1, %2, %3, %4, %5, %6, %7, %8, %9, %10, %11, %12, %13, %14, %15, %16, %17, %18, %19, %20, %21, %22, %23, %24, %25, %26, %27, %28, %29, %30, %31, %32, %33, %34, %35, %36, %37, %38, %39, %40, %41, %42, %43, %44, %45, %46, %47, %48, %49, %50, %51, %52, %53, %54, %55, %56, %57, %58, %59, %60, %61, %62, %63, %64, %65, %66, %67, %68, %69, %70, %71, %72, %73, %74, %75, %76, %77, %78, %79, %80, %81, %82, %83, %84, %85, %86, %87, %88, %89, %90, %91, %92, %93, %94, %95}, %96, %97, p, 1, 1, 0, 1;\n}\n"
    : "+f"(d[0]), "+f"(d[1]), "+f"(d[2]), "+f"(d[3]), "+f"(d[4]), "+f"(d[5]), "+f"(d[6]), "+f"(d[7]), "+f"(d[8]), "+f"(d[9]), "+f"(d[10]), "+f"(d[11]), "+f"(d[12]), "+f"(d[13]), "+f"(d[14]), "+f"(d[15]), "+f"(d[16]), "+f"(d[17]), "+f"(d[18]), "+f"(d[19]), "+f"(d[20]), "+f"(d[21]), "+f"(d[22]), "+f"(d[23]), "+f"(d[24]), "+f"(d[25]), "+f"(d[26]), "+f"(d[27]), "+f"(d[28]), "+f"(d[29]), "+f"(d[30]), "+f"(d[31]), "+f"(d[32]), "+f"(d[33]), "+f"(d[34]), "+f"(d[35]), "+f"(d[36]), "+f"(d[37]), "+f"(d[38]), "+f"(d[39]), "+f"(d[40]), "+f"(d[41]), "+f"(d[42]), "+f"(d[43]), "+f"(d[44]), "+f"(d[45]), "+f"(d[46]), "+f"(d[47]), "+f"(d[48]), "+f"(d[49]), "+f"(d[50]), "+f"(d[51]), "+f"(d[52]), "+f"(d[53]), "+f"(d[54]), "+f"(d[55]), "+f"(d[56]), "+f"(d[57]), "+f"(d[58]), "+f"(d[59]), "+f"(d[60]), "+f"(d[61]), "+f"(d[62]), "+f"(d[63]), "+f"(d[64]), "+f"(d[65]), "+f"(d[66]), "+f"(d[67]), "+f"(d[68]), "+f"(d[69]), "+f"(d[70]), "+f"(d[71]), "+f"(d[72]), "+f"(d[73]), "+f"(d[74]), "+f"(d[75]), "+f"(d[76]), "+f"(d[77]), "+f"(d[78]), "+f"(d[79]), "+f"(d[80]), "+f"(d[81]), "+f"(d[82]), "+f"(d[83]), "+f"(d[84]), "+f"(d[85]), "+f"(d[86]), "+f"(d[87]), "+f"(d[88]), "+f"(d[89]), "+f"(d[90]), "+f"(d[91]), "+f"(d[92]), "+f"(d[93]), "+f"(d[94]), "+f"(d[95]) : "l"(da), "l"(db), "r"(sc));
}
__device__ __forceinline__ void wg_ss_192_11(float (&d)[96], uint64_t da, uint64_t db, int sc) {
  asm volatile("{\n.reg .pred p;\nsetp.ne.b32 p, %98, 0;\n"
    "wgmma.mma_async.sync.aligned.m64n192k16.f32.bf16.bf16 {%0, %1, %2, %3, %4, %5, %6, %7, %8, %9, %10, %11, %12, %13, %14, %15, %16, %17, %18, %19, %20, %21, %22, %23, %24, %25, %26, %27, %28, %29, %30, %31, %32, %33, %34, %35, %36, %37, %38, %39, %40, %41, %42, %43, %44, %45, %46, %47, %48, %49, %50, %51, %52, %53, %54, %55, %56, %57, %58, %59, %60, %61, %62, %63, %64, %65, %66, %67, %68, %69, %70, %71, %72, %73, %74, %75, %76, %77, %78, %79, %80, %81, %82, %83, %84, %85, %86, %87, %88, %89, %90, %91, %92, %93, %94, %95}, %96, %97, p, 1, 1, 1, 1;\n}\n"
    : "+f"(d[0]), "+f"(d[1]), "+f"(d[2]), "+f"(d[3]), "+f"(d[4]), "+f"(d[5]), "+f"(d[6]), "+f"(d[7]), "+f"(d[8]), "+f"(d[9]), "+f"(d[10]), "+f"(d[11]), "+f"(d[12]), "+f"(d[13]), "+f"(d[14]), "+f"(d[15]), "+f"(d[16]), "+f"(d[17]), "+f"(d[18]), "+f"(d[19]), "+f"(d[20]), "+f"(d[21]), "+f"(d[22]), "+f"(d[23]), "+f"(d[24]), "+f"(d[25]), "+f"(d[26]), "+f"(d[27]), "+f"(d[28]), "+f"(d[29]), "+f"(d[30]), "+f"(d[31]), "+f"(d[32]), "+f"(d[33]), "+f"(d[34]), "+f"(d[35]), "+f"(d[36]), "+f"(d[37]), "+f"(d[38]), "+f"(d[39]), "+f"(d[40]), "+f"(d[41]), "+f"(d[42]), "+f"(d[43]), "+f"(d[44]), "+f"(d[45]), "+f"(d[46]), "+f"(d[47]), "+f"(d[48]), "+f"(d[49]), "+f"(d[50]), "+f"(d[51]), "+f"(d[52]), "+f"(d[53]), "+f"(d[54]), "+f"(d[55]), "+f"(d[56]), "+f"(d[57]), "+f"(d[58]), "+f"(d[59]), "+f"(d[60]), "+f"(d[61]), "+f"(d[62]), "+f"(d[63]), "+f"(d[64]), "+f"(d[65]), "+f"(d[66]), "+f"(d[67]), "+f"(d[68]), "+f"(d[69]), "+f"(d[70]), "+f"(d[71]), "+f"(d[72]), "+f"(d[73]), "+f"(d[74]), "+f"(d[75]), "+f"(d[76]), "+f"(d[77]), "+f"(d[78]), "+f"(d[79]), "+f"(d[80]), "+f"(d[81]), "+f"(d[82]), "+f"(d[83]), "+f"(d[84]), "+f"(d[85]), "+f"(d[86]), "+f"(d[87]), "+f"(d[88]), "+f"(d[89]), "+f"(d[90]), "+f"(d[91]), "+f"(d[92]), "+f"(d[93]), "+f"(d[94]), "+f"(d[95]) : "l"(da), "l"(db), "r"(sc));
}
__device__ __forceinline__ void wg_ss_8_10(float (&d)[4], uint64_t da, uint64_t db, int sc) {
  asm volatile("{\n.reg .pred p;\nsetp.ne.b32 p, %6, 0;\n"
    "wgmma.mma_async.sync.aligned.m64n8k16.f32.bf16.bf16 {%0, %1, %2, %3}, %4, %5, p, 1, 1, 1, 0;\n}\n"
    : "+f"(d[0]), "+f"(d[1]), "+f"(d[2]), "+f"(d[3]) : "l"(da), "l"(db), "r"(sc));
}
__device__ __forceinline__ void wg_rs_8_0(float (&d)[4], uint32_t a0, uint32_t a1, uint32_t a2, uint32_t a3, uint64_t db, int sc) {
  asm volatile("{\n.reg .pred p;\nsetp.ne.b32 p, %9, 0;\n"
    "wgmma.mma_async.sync.aligned.m64n8k16.f32.bf16.bf16 {%0, %1, %2, %3}, {%4,%5,%6,%7}, %8, p, 1, 1, 0;\n}\n"
    : "+f"(d[0]), "+f"(d[1]), "+f"(d[2]), "+f"(d[3]) : "r"(a0), "r"(a1), "r"(a2), "r"(a3), "l"(db), "r"(sc));
}
__device__ __forceinline__ void wg_rs_64_0(float (&d)[32], uint32_t a0, uint32_t a1, uint32_t a2, uint32_t a3, uint64_t db, int sc) {
  asm volatile("{\n.reg .pred p;\nsetp.ne.b32 p, %37, 0;\n"
    "wgmma.mma_async.sync.aligned.m64n64k16.f32.bf16.bf16 {%0, %1, %2, %3, %4, %5, %6, %7, %8, %9, %10, %11, %12, %13, %14, %15, %16, %17, %18, %19, %20, %21, %22, %23, %24, %25, %26, %27, %28, %29, %30, %31}, {%32,%33,%34,%35}, %36, p, 1, 1, 0;\n}\n"
    : "+f"(d[0]), "+f"(d[1]), "+f"(d[2]), "+f"(d[3]), "+f"(d[4]), "+f"(d[5]), "+f"(d[6]), "+f"(d[7]), "+f"(d[8]), "+f"(d[9]), "+f"(d[10]), "+f"(d[11]), "+f"(d[12]), "+f"(d[13]), "+f"(d[14]), "+f"(d[15]), "+f"(d[16]), "+f"(d[17]), "+f"(d[18]), "+f"(d[19]), "+f"(d[20]), "+f"(d[21]), "+f"(d[22]), "+f"(d[23]), "+f"(d[24]), "+f"(d[25]), "+f"(d[26]), "+f"(d[27]), "+f"(d[28]), "+f"(d[29]), "+f"(d[30]), "+f"(d[31]) : "r"(a0), "r"(a1), "r"(a2), "r"(a3), "l"(db), "r"(sc));
}
__device__ __forceinline__ void wg_rs_16_0(float (&d)[8], uint32_t a0, uint32_t a1, uint32_t a2, uint32_t a3, uint64_t db, int sc) {
  asm volatile("{\n.reg .pred p;\nsetp.ne.b32 p, %13, 0;\n"
    "wgmma.mma_async.sync.aligned.m64n16k16.f32.bf16.bf16 {%0, %1, %2, %3, %4, %5, %6, %7}, {%8,%9,%10,%11}, %12, p, 1, 1, 0;\n}\n"
    : "+f"(d[0]), "+f"(d[1]), "+f"(d[2]), "+f"(d[3]), "+f"(d[4]), "+f"(d[5]), "+f"(d[6]), "+f"(d[7]) : "r"(a0), "r"(a1), "r"(a2), "r"(a3), "l"(db), "r"(sc));
}
__device__ __forceinline__ void wg_rs_128_1(float (&d)[64], uint32_t a0, uint32_t a1, uint32_t a2, uint32_t a3, uint64_t db, int sc) {
  asm volatile("{\n.reg .pred p;\nsetp.ne.b32 p, %69, 0;\n"
    "wgmma.mma_async.sync.aligned.m64n128k16.f32.bf16.bf16 {%0, %1, %2, %3, %4, %5, %6, %7, %8, %9, %10, %11, %12, %13, %14, %15, %16, %17, %18, %19, %20, %21, %22, %23, %24, %25, %26, %27, %28, %29, %30, %31, %32, %33, %34, %35, %36, %37, %38, %39, %40, %41, %42, %43, %44, %45, %46, %47, %48, %49, %50, %51, %52, %53, %54, %55, %56, %57, %58, %59, %60, %61, %62, %63}, {%64,%65,%66,%67}, %68, p, 1, 1, 1;\n}\n"
    : "+f"(d[0]), "+f"(d[1]), "+f"(d[2]), "+f"(d[3]), "+f"(d[4]), "+f"(d[5]), "+f"(d[6]), "+f"(d[7]), "+f"(d[8]), "+f"(d[9]), "+f"(d[10]), "+f"(d[11]), "+f"(d[12]), "+f"(d[13]), "+f"(d[14]), "+f"(d[15]), "+f"(d[16]), "+f"(d[17]), "+f"(d[18]), "+f"(d[19]), "+f"(d[20]), "+f"(d[21]), "+f"(d[22]), "+f"(d[23]), "+f"(d[24]), "+f"(d[25]), "+f"(d[26]), "+f"(d[27]), "+f"(d[28]), "+f"(d[29]), "+f"(d[30]), "+f"(d[31]), "+f"(d[32]), "+f"(d[33]), "+f"(d[34]), "+f"(d[35]), "+f"(d[36]), "+f"(d[37]), "+f"(d[38]), "+f"(d[39]), "+f"(d[40]), "+f"(d[41]), "+f"(d[42]), "+f"(d[43]), "+f"(d[44]), "+f"(d[45]), "+f"(d[46]), "+f"(d[47]), "+f"(d[48]), "+f"(d[49]), "+f"(d[50]), "+f"(d[51]), "+f"(d[52]), "+f"(d[53]), "+f"(d[54]), "+f"(d[55]), "+f"(d[56]), "+f"(d[57]), "+f"(d[58]), "+f"(d[59]), "+f"(d[60]), "+f"(d[61]), "+f"(d[62]), "+f"(d[63]) : "r"(a0), "r"(a1), "r"(a2), "r"(a3), "l"(db), "r"(sc));
}

__global__ void __launch_bounds__(256) prologue_kernel(const bf16* __restrict__ x, const bf16* __restrict__ mem0) {
  const int warp = threadIdx.x >> 5, lane = threadIdx.x & 31;
  const int gt = blockIdx.x * 256 + threadIdx.x, NT = gridDim.x * 256;
  asm volatile("griddepcontrol.launch_dependents;" ::: "memory");
  STAMP(gt == 0, 0);
  const int row = blockIdx.x * 8 + warp;
  if (row < S_) {
    const uint32_t* xr = reinterpret_cast<const uint32_t*>(x + row * D_);
    float v[18];
#pragma unroll
    for (int i = 0; i < 9; i++) { uint32_t w = xr[lane + 32 * i]; v[2 * i] = __uint_as_float(w << 16); v[2 * i + 1] = __uint_as_float(w & 0xFFFF0000u); }
#pragma unroll
    for (int pass = 0; pass < 2; pass++) {
      float s = 0.f;
#pragma unroll
      for (int i = 0; i < 18; i++) s += v[i];
#pragma unroll
      for (int o = 16; o; o >>= 1) s += __shfl_xor_sync(~0u, s, o);
      const float mean = s * (1.f / D_);
      float q = 0.f;
#pragma unroll
      for (int i = 0; i < 18; i++) { v[i] -= mean; q += v[i] * v[i]; }
#pragma unroll
      for (int o = 16; o; o >>= 1) q += __shfl_xor_sync(~0u, q, o);
      const float r = 1.f / sqrtf(q * (1.f / D_) + 1e-5f);
      uint32_t* dst = reinterpret_cast<uint32_t*>((pass ? g_hb : g_xn) + row * D_);
#pragma unroll
      for (int i = 0; i < 9; i++) {
        uint32_t w = pack2(v[2 * i] * r, v[2 * i + 1] * r);
        dst[lane + 32 * i] = w;
        v[2 * i] = __uint_as_float(w << 16); v[2 * i + 1] = __uint_as_float(w & 0xFFFF0000u);
      }
    }
  }
  const uint4 z = make_uint4(0, 0, 0, 0);
  for (int i = gt; i < S_ * D_ / 4; i += NT) reinterpret_cast<uint4*>(g_acc)[i] = z;
  for (int i = gt; i < 4 * 1664; i += NT) reinterpret_cast<uint4*>(g_red)[i] = z;
  if (gt < 8 * 576) {
    int c = (gt % 576) >> 3, t = gt & 7;
    reinterpret_cast<uint4*>(g_mem)[gt] = *reinterpret_cast<const uint4*>(mem0 + t * D_ + c * 8);
  }
  for (int i = gt; i < C_TOT; i += NT) g_cnt[i] = 0;
}
constexpr int B_FULL = 0, B_EMPTY = 32, B_JFULL = 64, B_JEMPTY = 80, B_SFULL = 96, B_SEMPTY = 112, B_KVF = 128, B_KVE = 160,
              B_WLOAD = 192, B_WFREE = 200, B_S = 208, B_EXGO = 216, B_EXDN = 224, B_RSGO = 232, B_RSDN = 240, B_CHDN = 248,
              O_JOB = 256, B_X = 288, O_REQ = 320;
enum { J_KV, J_G1, J_FB, J_QA, J_FA, J_EXIT };

__device__ __forceinline__ int grp_size(int gi) { return (gi & 1) ? (gi == 31 ? 48 : 12) : 16; }
__device__ __forceinline__ int4 dec_dep(int gi, int r) {
  if (!(gi & 1)) return make_int4(J_QA, gi >> 1, r, 0);
  return make_int4(J_FA, gi >> 1, r % 3, r / 3);
}
__device__ __forceinline__ bool grp_ready(int gi) { return ld_acq(&g_cnt[((gi & 1) ? C_QAT : C_CH4) + (gi >> 1)]) >= 64; }
__device__ __forceinline__ int4 dec_ind(int idx) {
  if (idx < 512) return make_int4(J_KV, idx >> 5, idx & 31, 0);
  idx -= 512;
  if (idx < 108) return make_int4(J_G1, idx / 3, idx % 3, 0);
  idx -= 108;
  return make_int4(J_FB, idx / 6, idx % 3, (idx / 3) & 1);
}
__device__ __forceinline__ void deps(int4 j) {
  if (j.x == J_QA) {
    for (int i = 0; i < 4; i++) spin_ge(&g_cnt[C_PROG + (4 * j.z + i) * 32], 4 * j.y + 4);
    for (int i = 0; i < 2; i++) spin_ge(&g_cnt[C_KV + j.y * 32 + 2 * j.z + i], 4);
  } else if (j.x == J_FA) {
    const int n = j.y < 15 ? 4 : 1;
    for (int i = n - 1; i >= 0; i--) spin_ge(&g_cnt[C_QA + j.y * 16 + j.w * n + i], 4);
  } else if (j.x == J_FB) {
    spin_ge(&g_cnt[C_G1 + j.z], 36 * 4);
  }
}

__device__ __forceinline__ void worker_producer(const Params& P, uint32_t sb) {
  const uint32_t bar = sb + BAR_OFF;
  int it = 0, jn = 0, gi = 0;
  bool ind_left = true;
  auto acquire = [&](int bytes) -> uint32_t {
    const int st = it & (NST - 1);
    mbar_wait(bar + B_EMPTY + st * 8, ((it / NST) & 1) ^ 1);
    mbar_expect(bar + B_FULL + st * 8, bytes);
    return (uint32_t)st;
  };
  while (true) {
    int4 j = make_int4(J_EXIT, 0, 0, 0);
    while (true) {
      if (gi < 32 && (!ind_left || grp_ready(gi))) {
        const int r = atomicAdd(&g_cnt[C_DEP + gi], 1);
        if (r < grp_size(gi)) { j = dec_dep(gi, r); break; }
        gi++;
        continue;
      }
      if (!ind_left) break;
      const int i = atomicAdd(&g_cnt[C_IND], 1);
      if (i < N_IND) { j = dec_ind(i); break; }
      ind_left = false;
    }
    const int sl = jn & 1;
    mbar_wait(bar + B_JEMPTY + sl * 8, ((jn >> 1) & 1) ^ 1);
    asm volatile("st.shared.v4.b32 [%0], {%1,%2,%3,%4};" ::"r"(bar + O_JOB + sl * 16), "r"(j.x), "r"(j.y), "r"(j.z), "r"(j.w) : "memory");
    mbar_arrive(bar + B_JFULL + sl * 8);
    jn++;
    if (j.x == J_EXIT) break;
    if (j.x != J_QA) { deps(j); fence_async(); }
    if (j.x == J_KV || j.x == J_QA) {
      for (int kb = 0; kb < 9; kb++, it++) {
        const uint32_t st = acquire(49152), s = sb + st * STAGE, fb = bar + B_FULL + st * 8;
        tma_ld(s, &P.m[M_XN], kb * 64, j.y * 128, fb);
        if (j.x == J_KV) {
          for (int q = 0; q < 2; q++) {
            tma_ld(s + 16384 + q * 8192, &P.m[M_WK], j.z * 128 + q * 64, kb * 64, fb);
            tma_ld(s + 32768 + q * 8192, &P.m[M_WV], j.z * 128 + q * 64, kb * 64, fb);
          }
        } else {
          for (int q = 0; q < 4; q++) tma_ld(s + 16384 + q * 8192, &P.m[M_WQ], j.z * 256 + q * 64, kb * 64, fb);
        }
      }
      if (j.x == J_QA) {
        deps(j);
        fence_async();
        for (int u = 0; u < 4; u++, it++) {
          const uint32_t st = acquire(40960), s = sb + st * STAGE, fb = bar + B_FULL + st * 8;
          const int col = j.z * 256 + (u >> 1) * 128;
          for (int q = 0; q < 2; q++) {
            tma_ld(s + q * 16384, &P.m[(u & 1) ? M_V128 : M_K128], col + q * 64, j.y * 128, fb);
            tma_ld(s + 32768 + q * 4096, &P.m[(u & 1) ? M_MV : M_MK], col + q * 64, j.y * 32, fb);
          }
        }
      }
    } else {
      int nkb, k0, ma, mb;
      if (j.x == J_G1) { nkb = 32; k0 = 0; ma = M_W1; mb = M_HB; }
      else if (j.x == J_FB) { nkb = 36; k0 = j.w * 2304; ma = M_W2; mb = M_UT; }
      else { nkb = j.y < 15 ? 16 : 4; k0 = j.w * nkb * 64; ma = M_O128; mb = M_WO; }
      for (int kb = 0; kb < nkb; kb++, it++) {
        const uint32_t st = acquire(40960), s = sb + st * STAGE, fb = bar + B_FULL + st * 8;
        const int k = k0 + kb * 64;
        if (j.x == J_FA) tma_ld(s, &P.m[ma], k, j.y * 128, fb);
        else { tma_ld(s, &P.m[ma], j.y * 128, k, fb); tma_ld(s + 8192, &P.m[ma], j.y * 128 + 64, k, fb); }
        for (int q = 0; q < 3; q++) tma_ld(s + 16384 + q * 8192, &P.m[mb], j.z * 192 + q * 64, k, fb);
      }
    }
  }
}

__device__ __forceinline__ void store_warp(const Params& P, uint32_t sb, int wg) {
  const uint32_t bar = sb + BAR_OFF;
  for (int n = 0;; n++) {
    mbar_wait(bar + B_SFULL + wg * 8, n & 1);
    int mp, x, y, w;
    asm volatile("ld.shared.v4.b32 {%0,%1,%2,%3}, [%4];" : "=r"(mp), "=r"(x), "=r"(y), "=r"(w) : "r"(bar + O_REQ + wg * 16) : "memory");
    if (mp < 0) break;
    for (int q = 0; q < (w & 3); q++) tma_st(&P.m[mp], sb + STG_OFF + wg * 16384 + q * 8192, x + q * 64, y);
    asm volatile("cp.async.bulk.commit_group;" ::: "memory");
    asm volatile("cp.async.bulk.wait_group.read 0;" ::: "memory");
    mbar_arrive(bar + B_SEMPTY + wg * 8);
    asm volatile("cp.async.bulk.wait_group 0;" ::: "memory");
    fence_async();
    const int fl = w >> 2;
    red_rel(&g_cnt[fl], 1);
    if (fl >= C_QA && fl < C_KV) red_rel(&g_cnt[C_QAT + ((fl - C_QA) >> 4)], 1);
  }
}

template <int N, int TA>
__device__ __forceinline__ void mainloop(float (&acc)[N / 2], int nkb, int& it, uint32_t sb, int wg, int lane) {
  const uint32_t bar = sb + BAR_OFF;
  zero(acc);
  for (int kb = 0; kb < nkb; kb++, it++) {
    const int st = it & (NST - 1);
    mbar_wait(bar + B_FULL + st * 8, (it / NST) & 1);
    const uint32_t s = sb + st * STAGE;
    const uint64_t da = mkdesc(s + wg * 8192, 16, 1024, 1), db = mkdesc(s + 16384, 8192, 1024, 1);
    wg_fence();
#pragma unroll
    for (int k = 0; k < 4; k++) {
      const uint64_t a = da + (TA ? k * 128 : k * 2), b = db + k * 128;
      if constexpr (N == 256) wg_ss_256_01(acc, a, b, kb | k);
      else if constexpr (TA) wg_ss_192_11(acc, a, b, kb | k);
      else wg_ss_192_01(acc, a, b, kb | k);
    }
    wg_commit();
    if (kb > 0) { wg_wait<1>(); if (lane == 0) mbar_arrive(bar + B_EMPTY + ((it - 1) & (NST - 1)) * 8); }
  }
  wg_wait<0>();
  if (lane == 0) mbar_arrive(bar + B_EMPTY + ((it - 1) & (NST - 1)) * 8);
  keep(acc);
}

template <int NT, int T0, int NA>
__device__ __forceinline__ void store_round(const float (&ac)[NA], uint32_t sb, int wg, int& sn, int mp, int x, int y, int flag) {
  const uint32_t bar = sb + BAR_OFF;
  const int lane = threadIdx.x & 31, w = (threadIdx.x >> 5) & 3;
  mbar_wait(bar + B_SEMPTY + wg * 8, (sn & 1) ^ 1);
  const int mi = lane >> 3, row = 16 * w + (mi & 1) * 8 + (lane & 7);
  const uint32_t base = sb + STG_OFF + wg * 16384 + row * 128;
#pragma unroll
  for (int j = 0; j < NT; j += 2) {
    const int ch = j + (mi >> 1);
    const int b = 4 * (T0 + j);
    stsm4(base + (ch >> 3) * 8192 + (((ch & 7) ^ (row & 7)) << 4), pack2(ac[b], ac[b + 1]), pack2(ac[b + 2], ac[b + 3]),
          pack2(ac[b + 4], ac[b + 5]), pack2(ac[b + 6], ac[b + 7]));
  }
  fence_async_s();
  bar_sync(2 + wg, 128);
  if ((threadIdx.x & 127) == 0) {
    asm volatile("st.shared.v4.b32 [%0], {%1,%2,%3,%4};" ::"r"(bar + O_REQ + wg * 16), "r"(mp), "r"(x), "r"(y), "r"((NT / 8) | (flag << 2)) : "memory");
    mbar_arrive(bar + B_SFULL + wg * 8);
  }
  sn++;
}

__device__ __forceinline__ float gelu_t(float x) {
  float t, u = 0.7978845608028654f * (x + 0.044715f * x * x * x);
  asm("tanh.approx.f32 %0, %1;" : "=f"(t) : "f"(u));
  return 0.5f * x * (1.f + t);
}

__device__ __forceinline__ void worker_consumer(const Params& P, uint32_t sb, int wg) {
  const uint32_t bar = sb + BAR_OFF;
  const int lane = threadIdx.x & 31, w = (threadIdx.x >> 5) & 3, g = lane >> 2, cq = lane & 3;
  int it = 0, sn = 0;
  for (int jn = 0;; jn++) {
    const int sl = jn & 1;
    mbar_wait(bar + B_JFULL + sl * 8, (jn >> 1) & 1);
    int4 j;
    asm volatile("ld.shared.v4.b32 {%0,%1,%2,%3}, [%4];" : "=r"(j.x), "=r"(j.y), "=r"(j.z), "=r"(j.w) : "r"(bar + O_JOB + sl * 16) : "memory");
    j.x = __shfl_sync(~0u, j.x, 0); j.y = __shfl_sync(~0u, j.y, 0); j.z = __shfl_sync(~0u, j.z, 0); j.w = __shfl_sync(~0u, j.w, 0);
    if (lane == 0) mbar_arrive(bar + B_JEMPTY + sl * 8);
    if (j.x == J_EXIT) {
      mbar_wait(bar + B_SEMPTY + wg * 8, (sn & 1) ^ 1);
      bar_sync(2 + wg, 128);
      if ((threadIdx.x & 127) == 0) {
        asm volatile("st.shared.b32 [%0], %1;" ::"r"(bar + O_REQ + wg * 16), "r"(-1) : "memory");
        mbar_arrive(bar + B_SFULL + wg * 8);
      }
      break;
    }
    const int y = j.y * 128 + wg * 64;
    if (j.x == J_KV) {
      float acc[128];
      mainloop<256, 0>(acc, 9, it, sb, wg, lane);
      const int fl = C_KV + j.y * 32 + j.z;
      store_round<16, 0>(acc, sb, wg, sn, M_K64, j.z * 128, y, fl);
      store_round<16, 16>(acc, sb, wg, sn, M_V64, j.z * 128, y, fl);
    } else if (j.x == J_QA) {
      uint32_t pk[64];
      {
        float acc[128];
        mainloop<256, 0>(acc, 9, it, sb, wg, lane);
#pragma unroll
        for (int i = 0; i < 64; i++) { pk[i] = pack2(acc[2 * i], acc[2 * i + 1]); asm volatile("" : "+r"(pk[i])); }
      }
      {
        const float cs = 0.08838834764831845f * 1.4426950408889634f;
        const int sg = w >> 1, i0 = 16 * (w & 1) + g;
#pragma unroll
        for (int hh = 0; hh < 2; hh++) {
          float st[32], sm[8];
          zero(st); zero(sm);
          int stg = it & (NST - 1);
          mbar_wait(bar + B_FULL + stg * 8, (it / NST) & 1);
          uint32_t s = sb + stg * STAGE;
          wg_fence();
#pragma unroll
          for (int kk = 0; kk < 8; kk++) {
            const uint32_t* a = pk + 32 * hh + 4 * kk;
            wg_rs_64_0(st, a[0], a[1], a[2], a[3], mkdesc(s + (kk >> 2) * 16384 + wg * 8192 + (kk & 3) * 32, 16, 1024, 1), kk);
            wg_rs_16_0(sm, a[0], a[1], a[2], a[3], mkdesc(s + 32768 + (kk >> 2) * 4096 + wg * 2048 + (kk & 3) * 32, 16, 1024, 1), kk);
          }
          wg_commit();
          wg_wait<0>();
          keep(st); keep(sm);
          if (lane == 0) mbar_arrive(bar + B_EMPTY + stg * 8);
          it++;
          float mx0 = -INFINITY, mx1 = -INFINITY;
#pragma unroll
          for (int jj = 0; jj < 8; jj++)
#pragma unroll
            for (int e = 0; e < 2; e++) {
              const int c = (8 * jj + 2 * cq + e) & 31;
              const bool in = (jj >> 2) == sg;
              st[4 * jj + e] = (in && c <= i0) ? st[4 * jj + e] : -INFINITY;
              st[4 * jj + 2 + e] = (in && c <= i0 + 8) ? st[4 * jj + 2 + e] : -INFINITY;
              mx0 = fmaxf(mx0, st[4 * jj + e]); mx1 = fmaxf(mx1, st[4 * jj + 2 + e]);
            }
#pragma unroll
          for (int jj = 0; jj < 2; jj++)
#pragma unroll
            for (int e = 0; e < 2; e++) {
              sm[4 * jj + e] = jj == sg ? sm[4 * jj + e] : -INFINITY;
              sm[4 * jj + 2 + e] = jj == sg ? sm[4 * jj + 2 + e] : -INFINITY;
              mx0 = fmaxf(mx0, sm[4 * jj + e]); mx1 = fmaxf(mx1, sm[4 * jj + 2 + e]);
            }
          mx0 = fmaxf(mx0, __shfl_xor_sync(~0u, mx0, 1)); mx0 = fmaxf(mx0, __shfl_xor_sync(~0u, mx0, 2));
          mx1 = fmaxf(mx1, __shfl_xor_sync(~0u, mx1, 1)); mx1 = fmaxf(mx1, __shfl_xor_sync(~0u, mx1, 2));
          float s0 = 0.f, s1 = 0.f;
#pragma unroll
          for (int i = 0; i < 32; i++) { const bool hi = i & 2; st[i] = exp2f((st[i] - (hi ? mx1 : mx0)) * cs); if (hi) s1 += st[i]; else s0 += st[i]; }
#pragma unroll
          for (int i = 0; i < 8; i++) { const bool hi = i & 2; sm[i] = exp2f((sm[i] - (hi ? mx1 : mx0)) * cs); if (hi) s1 += sm[i]; else s0 += sm[i]; }
          s0 += __shfl_xor_sync(~0u, s0, 1); s0 += __shfl_xor_sync(~0u, s0, 2);
          s1 += __shfl_xor_sync(~0u, s1, 1); s1 += __shfl_xor_sync(~0u, s1, 2);
          s0 = 1.f / s0; s1 = 1.f / s1;
          uint32_t pf[20];
#pragma unroll
          for (int i = 0; i < 16; i++) { const float r = (i & 1) ? s1 : s0; pf[i] = pack2(st[2 * i] * r, st[2 * i + 1] * r); }
#pragma unroll
          for (int i = 0; i < 4; i++) { const float r = (i & 1) ? s1 : s0; pf[16 + i] = pack2(sm[2 * i] * r, sm[2 * i + 1] * r); }
          float o[64];
          zero(o);
          stg = it & (NST - 1);
          mbar_wait(bar + B_FULL + stg * 8, (it / NST) & 1);
          s = sb + stg * STAGE;
          wg_fence();
#pragma unroll
          for (int ks = 0; ks < 4; ks++)
            wg_rs_128_1(o, pf[4 * ks], pf[4 * ks + 1], pf[4 * ks + 2], pf[4 * ks + 3], mkdesc(s + wg * 8192 + ks * 2048, 16384, 1024, 1), ks);
          wg_rs_128_1(o, pf[16], pf[17], pf[18], pf[19], mkdesc(s + 32768 + wg * 2048, 4096, 1024, 1), 1);
          wg_commit();
          wg_wait<0>();
          keep(o);
          if (lane == 0) mbar_arrive(bar + B_EMPTY + stg * 8);
          it++;
          store_round<16, 0>(o, sb, wg, sn, M_O64, j.z * 256 + hh * 128, y, C_QA + j.y * 16 + j.z);
        }
      }
    } else {
      float acc[96];
      if (j.x == J_FA) mainloop<192, 0>(acc, j.y < 15 ? 16 : 4, it, sb, wg, lane);
      else mainloop<192, 1>(acc, j.x == J_G1 ? 32 : 36, it, sb, wg, lane);
      const int r0 = j.y * 128 + wg * 64 + 16 * w + g;
      if (j.x == J_G1) {
        const float b0 = __bfloat162float(P.b1[r0]), b1 = __bfloat162float(P.b1[r0 + 8]);
#pragma unroll
        for (int i = 0; i < 96; i++) acc[i] = gelu_t(acc[i] + ((i & 2) ? b1 : b0));
        store_round<16, 0>(acc, sb, wg, sn, M_UT, j.z * 192, y, C_G1 + j.z);
        store_round<8, 16>(acc, sb, wg, sn, M_UT, j.z * 192 + 128, y, C_G1 + j.z);
      } else {
        float* a0 = g_acc + r0 * D_ + j.z * 192 + 2 * cq;
#pragma unroll
        for (int i = 0; i < 24; i++) {
          asm volatile("red.global.add.v2.f32 [%0], {%1,%2};" ::"l"(a0 + 8 * i), "f"(acc[4 * i]), "f"(acc[4 * i + 1]) : "memory");
          asm volatile("red.global.add.v2.f32 [%0], {%1,%2};" ::"l"(a0 + 8 * D_ + 8 * i), "f"(acc[4 * i + 2]), "f"(acc[4 * i + 3]) : "memory");
        }
        __threadfence();
        bar_sync(2 + wg, 128);
        int last = 0;
        if ((threadIdx.x & 127) == 0) { last = atomicAdd(&g_cnt[C_FIN + (j.y * 3 + j.z) * 2 + wg], 1) == (j.y < 15 ? 5 : 17); __threadfence(); }
        int* sflag = reinterpret_cast<int*>(__cvta_shared_to_generic(bar + O_REQ + 32 + wg * 4));
        if ((threadIdx.x & 127) == 0) *sflag = last;
        bar_sync(2 + wg, 128);
        last = *sflag;
        if (last) {
          const int rb = j.y * 128 + wg * 64;
#pragma unroll 1
          for (int h = 0; h < 2; h++) {
            float4 a[12]; uint2 xv[12]; float bb[12];
#pragma unroll
            for (int k = 0; k < 12; k++) {
              const int i = (threadIdx.x & 127) + (h * 12 + k) * 128, r = rb + i / 48, c = j.z * 192 + (i % 48) * 4;
              a[k] = __ldcg(reinterpret_cast<const float4*>(g_acc + r * D_ + c));
              xv[k] = __ldg(reinterpret_cast<const uint2*>(P.x + r * D_ + c));
              bb[k] = __bfloat162float(__ldg(P.b2 + r));
            }
#pragma unroll
            for (int k = 0; k < 12; k++) {
              const int i = (threadIdx.x & 127) + (h * 12 + k) * 128, r = rb + i / 48, c = j.z * 192 + (i % 48) * 4;
              const float b = bb[k];
              uint2 o;
              o.x = pack2(a[k].x + b + __uint_as_float(xv[k].x << 16), a[k].y + b + __uint_as_float(xv[k].x & 0xFFFF0000u));
              o.y = pack2(a[k].z + b + __uint_as_float(xv[k].y << 16), a[k].w + b + __uint_as_float(xv[k].y & 0xFFFF0000u));
              *reinterpret_cast<uint2*>(P.out + r * D_ + c) = o;
            }
          }
        }
        bar_sync(2 + wg, 128);
      }
    }
    STAMP(dt, di + 3);
  }
}
#define DCTA 10
#define TT 0
constexpr int C_WV = 0, C_WO = 73728, C_KVS = 147456, C_MEM = 180224, C_Q = 189440, C_KM = 190464, C_VM = 191488,
              C_P = 193536, C_O = 194304, C_S = 195328, C_RED = 197888;

__device__ __forceinline__ void chain_producer(const Params& P, uint32_t sb, int cta) {
  const uint32_t bar = sb + BAR_OFF;
  const int h = cta >> 1, c0 = cta * 64;
  mbar_expect(bar + B_WLOAD, 147456);
  for (int q = 0; q < 9; q++) {
    tma_ld(sb + C_WV + q * 8192, &P.m[M_WQ], c0, q * 64, bar + B_WLOAD);
    tma_ld(sb + C_WO + q * 8192, &P.m[M_WK], c0, q * 64, bar + B_WLOAD);
  }
  mbar_wait(bar + B_WFREE, 0);
  mbar_expect(bar + B_WLOAD, 147456);
  for (int q = 0; q < 9; q++) {
    tma_ld(sb + C_WV + q * 8192, &P.m[M_WV], c0, q * 64, bar + B_WLOAD);
    tma_ld(sb + C_WO + q * 8192, &P.m[M_WO], q * 64, c0, bar + B_WLOAD);
  }
  griddep_wait();
  for (int s = 0; s < NSEG; s++) {
    if ((s & 3) == 0) { spin_ge(&g_cnt[C_KV + (s >> 2) * 32 + h], 4); fence_async(); }
    const int st = s & 3;
    mbar_wait(bar + B_KVE + st * 8, ((s >> 2) & 1) ^ 1);
    mbar_expect(bar + B_KVF + st * 8, 8192);
    tma_ld(sb + C_KVS + st * 8192, &P.m[M_K32], c0, s * 32, bar + B_KVF + st * 8);
    tma_ld(sb + C_KVS + st * 8192 + 4096, &P.m[M_V32], c0, s * 32, bar + B_KVF + st * 8);
  }
}
__device__ __forceinline__ void chain_export(uint32_t sb, int cta, int lane) {
  const uint32_t bar = sb + BAR_OFF;
  for (int s = 0; s < NSEG; s++) {
    mbar_wait(bar + B_EXGO, s & 1);
    uint4 v[4];
#pragma unroll
    for (int i = 0; i < 4; i++) {
      const int id = lane + 32 * (i & 1), t = id >> 3, c = id & 7;
      asm volatile("ld.shared.v4.b32 {%0,%1,%2,%3}, [%4];" : "=r"(v[i].x), "=r"(v[i].y), "=r"(v[i].z), "=r"(v[i].w)
                   : "r"(sb + (i < 2 ? C_KM : C_VM) + t * 128 + ((c ^ t) << 4)) : "memory");
    }
    __syncwarp();
    if (lane == 0) mbar_arrive(bar + B_EXDN);
    if (s < NSEG - 1) mbar_wait(bar + B_RSGO, s & 1);
#pragma unroll
    for (int i = 0; i < 4; i++) {
      const int id = lane + 32 * (i & 1), t = id >> 3, c = id & 7;
      *reinterpret_cast<uint4*>((i < 2 ? g_mK : g_mV) + (s * 8 + t) * HD + cta * 64 + c * 8) = v[i];
    }
    __threadfence();
    __syncwarp();
    if (lane == 0) { red_rel(&g_cnt[C_PROG + cta * 32], 1); if ((s & 3) == 3) red_rel(&g_cnt[C_CH4 + (s >> 2)], 1); }
  }
}
__device__ __forceinline__ void chain_reset(uint32_t sb, int cta, int lane) {
  const uint32_t bar = sb + BAR_OFF;
  for (int n = 0; n < NSEG - 1; n++) {
    mbar_wait(bar + B_RSGO, n & 1);
    if (n >= 1 && lane < 26) __stcg(reinterpret_cast<uint4*>(g_red) + ((n - 1) & 3) * 1664 + cta * 26 + lane, make_uint4(0, 0, 0, 0));
    __threadfence();
    __syncwarp();
    if (lane == 0) mbar_arrive(bar + B_RSDN);
  }
}

#define PDL_ON 0
#define DLY_MEM 1400
#define DLY_RS 900
__device__ __forceinline__ void delay_clk(int d) {
  if (d > 0) { uint32_t t0, t; asm volatile("mov.u32 %0, %%clock;" : "=r"(t0)); do { asm volatile("mov.u32 %0, %%clock;" : "=r"(t)); } while ((int)(t - t0) < d); }
}
template <int wg>
__device__ __forceinline__ void chain_consumer(uint32_t sb, int cta) {
  const uint32_t bar = sb + BAR_OFF;
  const int tid = threadIdx.x, lane = tid & 31, warp = __shfl_sync(~0u, tid >> 5, 0), w = warp & 3, g = lane >> 2, cq = lane & 3;
  const uint32_t rank = cta & 1;
  if (tid < 64) asm volatile("st.shared.v4.b32 [%0], {%1,%1,%1,%1};" ::"r"(sb + C_VM + 1024 + tid * 16), "r"(0) : "memory");
  else if (tid < 72) asm volatile("st.shared.v4.b32 [%0], {%1,%1,%1,%1};" ::"r"(sb + C_P + 640 + (tid - 64) * 16), "r"(0) : "memory");
  STAMP(cta == DCTA && tid == 0, 1);
  uint32_t wr[144];
  mbar_wait(bar + B_WLOAD, 0);
  {
    const int mi = lane >> 3;
#pragma unroll
    for (int ks = 0; ks < 36; ks++) {
      const int k = 16 * ks + (mi >> 1) * 8 + (lane & 7), ch = 2 * w + (mi & 1);
      ldsm4t(sb + (wg ? C_WO : C_WV) + k * 128 + ((ch ^ (k & 7)) << 4), wr[4 * ks], wr[4 * ks + 1], wr[4 * ks + 2], wr[4 * ks + 3]);
    }
  }
  bar_sync(1, 256);
  if (tid == 0) mbar_arrive(bar + B_WFREE);
  uint32_t s_loc, s_rem, sb_loc, sb_rem;
  asm volatile("mapa.shared::cluster.u32 %0, %1, %2;" : "=r"(s_loc) : "r"(sb + C_S + rank * 1280), "r"(rank));
  asm volatile("mapa.shared::cluster.u32 %0, %1, %2;" : "=r"(s_rem) : "r"(sb + C_S + rank * 1280), "r"(rank ^ 1));
  asm volatile("mapa.shared::cluster.u32 %0, %1, %2;" : "=r"(sb_loc) : "r"(bar + B_S), "r"(rank));
  asm volatile("mapa.shared::cluster.u32 %0, %1, %2;" : "=r"(sb_rem) : "r"(bar + B_S), "r"(rank ^ 1));
  mbar_wait(bar + B_WLOAD, 1);
  for (int t = 9 + warp; t < 18; t += 8) {
    const uint32_t T = sb + t * 8192, r = lane & 7, jj = lane >> 3;
#pragma unroll
    for (int i = 0; i < 4; i++)
#pragma unroll
      for (int j = i; j < 4; j++) {
        const uint32_t a = 2 * i + (jj >> 1), b = 2 * j + (jj & 1), a2 = 2 * j + (jj >> 1), b2 = 2 * i + (jj & 1);
        uint32_t x0, x1, x2, x3, y0 = 0, y1 = 0, y2 = 0, y3 = 0;
        ldsm4t(T + (a * 8 + r) * 128 + ((b ^ r) << 4), x0, x1, x2, x3);
        if (i != j) ldsm4t(T + (a2 * 8 + r) * 128 + ((b2 ^ r) << 4), y0, y1, y2, y3);
        __syncwarp();
        stsm4(T + (b * 8 + r) * 128 + ((a ^ r) << 4), x0, x1, x2, x3);
        if (i != j) stsm4(T + (b2 * 8 + r) * 128 + ((a2 ^ r) << 4), y0, y1, y2, y3);
        __syncwarp();
      }
  }
  fence_async_s();
  bar_sync(1, 256);
  griddep_wait();
  STAMP(cta == DCTA && tid == 0, 2);
  const uint32_t sb0 = sb;
  for (int s = 0; s < NSEG; s++) {
    uint32_t sb = sb0;
    asm volatile("" : "+r"(sb));
    const uint32_t bar = sb + BAR_OFF;
    const uint64_t dmem = mkdesc(sb + C_MEM, 128, 128, 0);
    if (tid == 0) { mbar_expect(bar + B_S, 2560); if (s < NSEG - 1) mbar_expect(bar + B_X, rank ? 12288 : 14336); }
    STAMP(cta == DCTA && tid == 0, 600 + s);
    if (s == 0) {
      const uint4* src = reinterpret_cast<const uint4*>(g_mem) + (cta & 7) * 576;
#pragma unroll
      for (int i = 0; i < 3; i++)
        if (i < 2 || tid < 64) {
          const uint4 v = __ldcg(src + tid + 256 * i);
          asm volatile("st.shared.v4.b32 [%0], {%1,%2,%3,%4};" ::"r"(sb + C_MEM + (tid + 256 * i) * 16), "r"(v.x), "r"(v.y), "r"(v.z), "r"(v.w) : "memory");
        }
    } else {
      constexpr int NP = wg ? 6 : 7;
      const float4* src = g_red + ((s - 1) & 3) * 1664 + tid;
      float4 v[NP];
      int n = 0;
      uint32_t pend = (1u << NP) - 1;
      delay_clk(DLY_MEM);
      do {
#pragma unroll
        for (int i = 0; i < NP; i++)
          if (pend >> i & 1)
            asm volatile("ld.relaxed.gpu.global.v4.f32 {%0,%1,%2,%3}, [%4];" : "=f"(v[i].x), "=f"(v[i].y), "=f"(v[i].z), "=f"(v[i].w) : "l"(src + 256 * i) : "memory");
#pragma unroll
        for (int i = 0; i < NP; i++)
          if ((pend >> i & 1) && v[i].w == (float)(NCHAIN / 2)) pend &= ~(1u << i);
        TRAP_IF(++n, SPIN_LIMIT >> 4);
      } while (pend);
      float m[3 * NP];
#pragma unroll
      for (int i = 0; i < NP; i++) { m[3 * i] = v[i].x; m[3 * i + 1] = v[i].y; m[3 * i + 2] = v[i].z; }
#pragma unroll
      for (int i = 0; i < (wg ? 4 : 5); i++)
        stsm2t(sb + C_MEM + (2 * (warp + 8 * i) + ((lane >> 3) & 1)) * 128 + (lane & 7) * 16, pack2(m[4 * i], m[4 * i + 1]), pack2(m[4 * i + 2], m[4 * i + 3]));
    }
    fence_async_s();
    bar_sync(1, 256);

    if (tid == 128 && s > 0) { mbar_wait(bar + B_EXDN, (s - 1) & 1); mbar_arrive(bar + B_RSGO); }
    STAMPC(cta == DCTA && tid == 0, 16 + s * 8);
    float a0[4], a1[4], a2[4], a3[4], av[4][4];
    zero(a0); zero(a1); zero(a2); zero(a3); zero(av[0]); zero(av[1]); zero(av[2]); zero(av[3]);
    {
      const uint32_t mb = sb + C_MEM + (lane >> 3) * 128 + (lane & 7) * 16;
#pragma unroll
      for (int i = 0; i < 9; i++) {
        uint32_t b0, b1, b2, b3, b4, b5, b6, b7;
        ldsm4(mb + i * 1024, b0, b1, b2, b3);
        ldsm4(mb + i * 1024 + 512, b4, b5, b6, b7);
        const uint32_t* q = wr + 16 * i;
        mma16816(a0, q[0], q[1], q[2], q[3], b0, b1);
        mma16816(a1, q[4], q[5], q[6], q[7], b2, b3);
        mma16816(a2, q[8], q[9], q[10], q[11], b4, b5);
        mma16816(a3, q[12], q[13], q[14], q[15], b6, b7);
      }
#pragma unroll
      for (int i = 0; i < 4; i++) a0[i] = (a0[i] + a1[i]) + (a2[i] + a3[i]);
    }
    if (s > 0) mbar_wait(bar + B_EXDN, (s - 1) & 1);
    const uint32_t trow = (lane & 7) * 128 + (((2 * w + ((lane >> 3) & 1)) ^ (lane & 7)) << 4);
    stsm2t(sb + (wg ? C_KM : C_Q) + trow, pack2(a0[0], a0[1]), pack2(a0[2], a0[3]));
    bar_sync(1, 256);
    STAMPC(cta == DCTA && tid == 0, 17 + s * 8);
    const uint32_t kvs = sb + C_KVS + (s & 3) * 8192;
    if (wg == 0 || w == 0) {
      if (wg == 0) mbar_wait(bar + B_KVF + (s & 3) * 8, (s >> 2) & 1);
      const uint32_t qb = sb + C_Q + (lane & 7) * 128;
      const uint32_t off0 = (((lane >> 3)) ^ (lane & 7)) << 4, off1 = ((4 + (lane >> 3)) ^ (lane & 7)) << 4;
      const int tile = wg ? 4 : w;
      const uint32_t kb = (wg ? sb + C_KM : kvs + w * 1024) + (lane & 7) * 128;
      uint32_t q[8], k[8];
      ldsm4(qb + off0, q[0], q[1], q[2], q[3]); ldsm4(kb + off0, k[0], k[1], k[2], k[3]);
      ldsm4(qb + off1, q[4], q[5], q[6], q[7]); ldsm4(kb + off1, k[4], k[5], k[6], k[7]);
      float c0[4] = {0.f, 0.f, 0.f, 0.f}, c1[4] = {0.f, 0.f, 0.f, 0.f};
      mma16816(c0, q[0], 0, q[1], 0, k[0], k[1]); mma16816(c1, q[4], 0, q[5], 0, k[4], k[5]);
      mma16816(c0, q[2], 0, q[3], 0, k[2], k[3]); mma16816(c1, q[6], 0, q[7], 0, k[6], k[7]);
      const float x = c0[0] + c1[0], y = c0[1] + c1[1];
      const uint32_t o = tile * 256 + lane * 8;
      asm volatile("st.async.weak.shared::cluster.mbarrier::complete_tx::bytes.v2.f32 [%0], {%1,%2}, [%3];" ::"r"(s_rem + o), "f"(x), "f"(y), "r"(sb_rem) : "memory");
      asm volatile("st.async.weak.shared::cluster.mbarrier::complete_tx::bytes.v2.f32 [%0], {%1,%2}, [%3];" ::"r"(s_loc + o), "f"(x), "f"(y), "r"(sb_loc) : "memory");
    }
    if (wg == 1) {
      bar_sync(4, 256);
      const uint64_t dv = mkdesc(sb + C_WV, 16, 1024, 1);
      wg_fence();
#pragma unroll
      for (int ks = 0; ks < 36; ks++) wg_ss_8_10(av[ks & 3], dv + ks * 128, dmem + ks * 16, ks >> 2);
      wg_commit();
    } else {
      asm volatile("bar.arrive 4, 256;" ::: "memory");
    }
    if (warp == 0) {
      mbar_wait_cl(bar + B_S, s & 1);
      STAMPC(cta == DCTA && tid == 0, 18 + s * 8);
      float p[10], mx = -INFINITY;
#pragma unroll
      for (int t = 0; t < 5; t++) {
        float2 u, v;
        asm volatile("ld.shared.v2.f32 {%0,%1}, [%2];" : "=f"(u.x), "=f"(u.y) : "r"(sb + C_S + t * 256 + lane * 8) : "memory");
        asm volatile("ld.shared.v2.f32 {%0,%1}, [%2];" : "=f"(v.x), "=f"(v.y) : "r"(sb + C_S + 1280 + t * 256 + lane * 8) : "memory");
        p[2 * t] = u.x + v.x; p[2 * t + 1] = u.y + v.y;
        mx = fmaxf(mx, fmaxf(p[2 * t], p[2 * t + 1]));
      }
      mx = fmaxf(mx, __shfl_xor_sync(~0u, mx, 1)); mx = fmaxf(mx, __shfl_xor_sync(~0u, mx, 2));
      const float cs = 0.08838834764831845f * 1.4426950408889634f;
      float sum = 0.f;
#pragma unroll
      for (int i = 0; i < 10; i++) { p[i] = exp2f((p[i] - mx) * cs); sum += p[i]; }
#pragma unroll
      for (int t = 0; t < 5; t++)
        asm volatile("st.shared.b32 [%0], %1;" ::"r"(sb + C_P + t * 128 + g * 16 + cq * 4), "r"(pack2(p[2 * t], p[2 * t + 1])) : "memory");
      sum += __shfl_xor_sync(~0u, sum, 1); sum += __shfl_xor_sync(~0u, sum, 2);
      if (cq == 0) asm volatile("st.shared.f32 [%0], %1;" ::"r"(sb + C_Q + g * 4), "f"(sum) : "memory");
      fence_async_s();
    }
    if (wg == 1) {
      wg_wait<0>();
      keep(av[0]); keep(av[1]); keep(av[2]); keep(av[3]);
#pragma unroll
      for (int i = 0; i < 4; i++) av[0][i] = (av[0][i] + av[1][i]) + (av[2][i] + av[3][i]);
      stsm2t(sb + C_VM + trow, pack2(av[0][0], av[0][1]), pack2(av[0][2], av[0][3]));
      fence_async_s();
    }
    bar_sync(1, 256);
    STAMPC(cta == DCTA && tid == 0, 19 + s * 8);
    if (tid == 128) mbar_arrive(bar + B_EXGO);
    if (s == NSEG - 1) break;
    if (wg == 0) {
      float o[4], o2[4], o3[4];
      zero(o); zero(o2); zero(o3);
      const uint64_t dp = mkdesc(sb + C_P, 128, 128, 0);
      wg_fence();
      wg_ss_8_10(o, mkdesc(kvs + 4096, 16, 1024, 1), dp, 0);
      wg_ss_8_10(o2, mkdesc(kvs + 4096 + 2048, 16, 1024, 1), dp + 16, 0);
      wg_ss_8_10(o3, mkdesc(sb + C_VM, 16, 1024, 1), dp + 32, 0);
      wg_commit();
      float r0, r1;
      asm volatile("ld.shared.v2.f32 {%0,%1}, [%2];" : "=f"(r0), "=f"(r1) : "r"(sb + C_Q + cq * 8) : "memory");
      r0 = __frcp_rn(r0); r1 = __frcp_rn(r1);
      wg_wait<0>();
      keep(o); keep(o2); keep(o3);
#pragma unroll
      for (int i = 0; i < 4; i++) o[i] += o2[i] + o3[i];
      if (lane == 0) mbar_arrive(bar + B_KVE + (s & 3) * 8);
      stsm2t(sb + C_O + (2 * w + ((lane >> 3) & 1)) * 128 + (lane & 7) * 16, pack2(o[0] * r0, o[1] * r1), pack2(o[2] * r0, o[3] * r1));
    }
    bar_sync(1, 256);
    STAMPC(cta == DCTA && tid == 0, 20 + s * 8);
    {
      float d[5][4];
#pragma unroll
      for (int i = 0; i < 5; i++) zero(d[i]);
      {
        uint32_t b[8];
        const uint32_t ob = sb + C_O + (lane >> 3) * 128 + (lane & 7) * 16;
        ldsm4(ob, b[0], b[1], b[2], b[3]); ldsm4(ob + 512, b[4], b[5], b[6], b[7]);
        const uint32_t r = (lane & 7) + ((lane >> 3) & 1) * 8;
        const uint32_t ab = sb + C_WO + (warp * 16 + r) * 128;
#pragma unroll
        for (int ks = 0; ks < 4; ks++)
#pragma unroll
          for (int i = 0; i < 5; i++)
            if (i < 4 || wg == 0) {
              uint32_t a0_, a1_, a2_, a3_;
              ldsm4(ab + i * 16384 + (((2 * ks + (lane >> 4)) ^ (lane & 7)) << 4), a0_, a1_, a2_, a3_);
              mma16816(d[i], a0_, a1_, a2_, a3_, b[2 * ks], b[2 * ks + 1]);
            }
      }
      constexpr int NP = wg ? 6 : 7;
      float m[3 * NP];
#pragma unroll
      for (int i = 0; i < 3 * NP; i++) m[i] = i < (wg ? 16 : 20) ? d[i >> 2][i & 3] : 0.f;
      const uint32_t x_rem = s_rem + (C_RED - C_S) - rank * 1280 + tid * 16, xb_rem = sb_rem + (B_X - B_S);
#pragma unroll
      for (int p = 0; p < NP; p++)
        if ((p & 1) != rank)
          asm volatile("st.async.weak.shared::cluster.mbarrier::complete_tx::bytes.v4.f32 [%0], {%1,%2,%3,%4}, [%5];" ::"r"(x_rem + (p >> 1) * 4096),
                       "f"(m[3 * p]), "f"(m[3 * p + 1]), "f"(m[3 * p + 2]), "f"(0.f), "r"(xb_rem) : "memory");
      if (s > 0) mbar_wait(bar + B_RSDN, (s - 1) & 1);
      mbar_wait_cl(bar + B_X, s & 1);
      float4* dst = g_red + (s & 3) * 1664 + tid;
#pragma unroll
      for (int p = 0; p < NP; p++)
        if ((p & 1) == rank) {
          float4 o;
          asm volatile("ld.shared.v4.f32 {%0,%1,%2,%3}, [%4];" : "=f"(o.x), "=f"(o.y), "=f"(o.z), "=f"(o.w) : "r"(sb + C_RED + (p >> 1) * 4096 + tid * 16) : "memory");
          asm volatile("red.relaxed.gpu.global.add.v4.f32 [%0], {%1,%2,%3,%4};" ::"l"(dst + 256 * p), "f"(m[3 * p] + o.x), "f"(m[3 * p + 1] + o.y), "f"(m[3 * p + 2] + o.z), "f"(1.f) : "memory");
        }
    }
    STAMPC(cta == DCTA && tid == 0, 21 + s * 8); STAMPC(cta == DCTA && tid == 0, 22 + s * 8); STAMPC(cta == DCTA && tid == 0, 23 + s * 8);
  }
}

__global__ void __cluster_dims__(2, 1, 1) __launch_bounds__(384, 1) main_kernel(const __grid_constant__ Params P) {
  extern __shared__ __align__(1024) uint8_t smem[];
  const uint32_t sb = smem_u32(smem), bar = sb + BAR_OFF;
  const int wg = __shfl_sync(~0u, threadIdx.x >> 7, 0), cta = blockIdx.x;
  if (threadIdx.x == 0) {
    for (int i = 0; i < 4; i++) { mbar_init(bar + B_FULL + i * 8, 1); mbar_init(bar + B_EMPTY + i * 8, 8); mbar_init(bar + B_KVF + i * 8, 1); mbar_init(bar + B_KVE + i * 8, 4); }
    for (int i = 0; i < 2; i++) { mbar_init(bar + B_JFULL + i * 8, 1); mbar_init(bar + B_JEMPTY + i * 8, 8); mbar_init(bar + B_SFULL + i * 8, 1); mbar_init(bar + B_SEMPTY + i * 8, 1); }
    mbar_init(bar + B_WLOAD, 1); mbar_init(bar + B_WFREE, 1); mbar_init(bar + B_S, 1); mbar_init(bar + B_EXGO, 1);
    mbar_init(bar + B_EXDN, 1); mbar_init(bar + B_RSGO, 1); mbar_init(bar + B_RSDN, 1); mbar_init(bar + B_CHDN, 8); mbar_init(bar + B_X, 1);
    asm volatile("fence.mbarrier_init.release.cluster;" ::: "memory");
  }
  __syncthreads();
  asm volatile("barrier.cluster.arrive.release.aligned;\nbarrier.cluster.wait.acquire.aligned;" ::: "memory");
  const bool chain = cta < NCHAIN;
  if (wg == 2) {
    asm volatile("setmaxnreg.dec.sync.aligned.u32 40;");
    const int warp = (threadIdx.x >> 5) & 3, lane = threadIdx.x & 31;
    if (!(chain && warp == 0)) griddep_wait();
    if (chain) {
      if (warp == 0) { if (lane == 0) chain_producer(P, sb, cta); }
      else if (warp == 1) chain_export(sb, cta, lane);
      else if (warp == 2) chain_reset(sb, cta, lane);
      __syncwarp();
    }
    if (lane == 0) {
      if (warp == 0) { if (chain) mbar_wait(bar + B_CHDN, 0); worker_producer(P, sb); }
      else if (warp < 3) store_warp(P, sb, warp - 1);
    }
  } else {
    asm volatile("setmaxnreg.inc.sync.aligned.u32 232;");
    if (!chain) griddep_wait();
    if (chain) {
      if (wg == 0) chain_consumer<0>(sb, cta); else chain_consumer<1>(sb, cta);
      fence_async_s();
      bar_sync(1, 256);
      if ((threadIdx.x & 31) == 0) mbar_arrive(bar + B_CHDN);
    }
    worker_consumer(P, sb, wg);
  }
}

typedef CUresult (*EncFn)(CUtensorMap*, CUtensorMapDataType, cuuint32_t, void*, const cuuint64_t*, const cuuint64_t*, const cuuint32_t*, const cuuint32_t*,
                          CUtensorMapInterleave, CUtensorMapSwizzle, CUtensorMapL2promotion, CUtensorMapFloatOOBfill);
static void mkmap(EncFn fn, CUtensorMap* m, const void* p, int rows, int cols, int boxr) {
  cuuint64_t dim[2] = {(cuuint64_t)cols, (cuuint64_t)rows}, str[1] = {(cuuint64_t)cols * 2};
  cuuint32_t box[2] = {64, (cuuint32_t)boxr}, es[2] = {1, 1};
  fn(m, CU_TENSOR_MAP_DATA_TYPE_BFLOAT16, 2, const_cast<void*>(p), dim, str, box, es, CU_TENSOR_MAP_INTERLEAVE_NONE, CU_TENSOR_MAP_SWIZZLE_128B,
     CU_TENSOR_MAP_L2_PROMOTION_L2_128B, CU_TENSOR_MAP_FLOAT_OOB_FILL_NONE);
}
template <class T> static void* sym(T& s) { void* p = nullptr; cudaGetSymbolAddress(&p, s); return p; }

extern "C" void kernel_launch(void* const* d_in, const int* in_sizes, int n_in, void* d_out, int out_size) {
  static Params P;
  static int grid = 0;
  static const void* key[13];
  const bf16 *x = (const bf16*)d_in[0], *mem0 = (const bf16*)d_in[1];
  bool same = grid != 0 && key[12] == d_out;
  for (int i = 0; i < 12 && same; i++) same = key[i] == d_in[i];
  if (!same) {
    for (int i = 0; i < 12; i++) key[i] = d_in[i];
    key[12] = d_out;
    void* f = nullptr; cudaDriverEntryPointQueryResult qr;
    cudaGetDriverEntryPoint("cuTensorMapEncodeTiled", &f, cudaEnableDefault, &qr);
    EncFn fn = (EncFn)f;
    mkmap(fn, &P.m[M_XN], sym(g_xn), S_, D_, 128);
    mkmap(fn, &P.m[M_WQ], d_in[2], D_, HD, 64); mkmap(fn, &P.m[M_WK], d_in[3], D_, HD, 64); mkmap(fn, &P.m[M_WV], d_in[4], D_, HD, 64);
    mkmap(fn, &P.m[M_WO], d_in[5], HD, D_, 64);
    mkmap(fn, &P.m[M_W1], d_in[8], S_, F_, 64); mkmap(fn, &P.m[M_HB], sym(g_hb), S_, D_, 64);
    mkmap(fn, &P.m[M_W2], d_in[10], F_, S_, 64); mkmap(fn, &P.m[M_UT], sym(g_uT), F_, D_, 64);
    mkmap(fn, &P.m[M_K128], sym(g_K), S_, HD, 128); mkmap(fn, &P.m[M_K32], sym(g_K), S_, HD, 32); mkmap(fn, &P.m[M_K64], sym(g_K), S_, HD, 64);
    mkmap(fn, &P.m[M_V128], sym(g_V), S_, HD, 128); mkmap(fn, &P.m[M_V32], sym(g_V), S_, HD, 32); mkmap(fn, &P.m[M_V64], sym(g_V), S_, HD, 64);
    mkmap(fn, &P.m[M_O128], sym(g_O), S_, HD, 128); mkmap(fn, &P.m[M_O64], sym(g_O), S_, HD, 64);
    mkmap(fn, &P.m[M_MK], sym(g_mK), NSEG * 8, HD, 32); mkmap(fn, &P.m[M_MV], sym(g_mV), NSEG * 8, HD, 32);
    P.x = x; P.b1 = (const bf16*)d_in[9]; P.b2 = (const bf16*)d_in[11]; P.out = (bf16*)d_out;
    cudaFuncSetAttribute(main_kernel, cudaFuncAttributeMaxDynamicSharedMemorySize, SMEM_BYTES);
    int sms = 0; cudaDeviceGetAttribute(&sms, cudaDevAttrMultiProcessorCount, 0);
    grid = sms & ~1;
  }
  cudaStream_t st = cudaStreamPerThread;
  prologue_kernel<<<256, 256, 0, st>>>(x, mem0);
  cudaLaunchConfig_t cfg = {};
  cfg.gridDim = dim3(grid); cfg.blockDim = dim3(384); cfg.dynamicSmemBytes = SMEM_BYTES; cfg.stream = st;
  cudaLaunchAttribute at[1];
  at[0].id = cudaLaunchAttributeProgrammaticStreamSerialization;
  at[0].val.programmaticStreamSerializationAllowed = 1;
  cfg.attrs = at; cfg.numAttrs = PDL_ON;
  cudaLaunchKernelEx(&cfg, main_kernel, P);
}
```
